```python
import torch

def _softmax(x, axis=-1):
    return torch.softmax(x, dim=axis)

def _gelu(x):
    return torch.nn.functional.gelu(x, approximate='tanh')

def _silu(x):
    return torch.nn.functional.silu(x)

def _sigmoid(x):
    return torch.sigmoid(x)

def _layernorm(x, axis=-1, eps=1e-05):
    m = x.mean(dim=axis, keepdim=True)
    v = x.var(dim=axis, keepdim=True, unbiased=False)
    return (x - m) / torch.sqrt(v + eps)

def _scatter_add(tgt, idx, src, axis=0):
    return tgt.clone().index_add_(axis, idx, src)

def _segment_sum(src, seg, n):
    out = torch.zeros((n,) + src.shape[1:], dtype=src.dtype)
    return out.index_add_(0, seg, src)

def _pad(x, pw):
    flat = tuple((v for pair in reversed(pw) for v in pair))
    return torch.nn.functional.pad(x, flat)
kernel_name = 'adaLN_cond__sliding_block_cached__swiglu_ffn__prompt'

def setup_inputs():

    _w = lambda a: (lambda t: t.to(torch.bfloat16) if t.is_floating_point() else t)(torch.as_tensor(a))

    def _A_setup():
        B, Sq, D = (1, 2048, 640)
        Hq, Hkv, Sk, Dh = (32, 32, 2048, 128)
        assert Hq % Hkv == 0, (Hq, Hkv)
        return {'x': _w((lambda *s: torch.randn(*s, dtype=torch.bfloat16) * 0.05)(B, Sq, D)), 'k_cache': _w((lambda *s: torch.randn(*s, dtype=torch.bfloat16) * 3.2)(B, Hkv, Sk, Dh)), 'v_cache': _w((lambda *s: torch.randn(*s, dtype=torch.bfloat16) * 0.4)(B, Hkv, Sk, Dh)), 'wq': _w((lambda *s: torch.randn(*s, dtype=torch.bfloat16) * 3.2)(D, Hq * Dh) * D ** (-0.5)), 'wo': _w((lambda *s: torch.randn(*s, dtype=torch.bfloat16) * 0.4)(Hq * Dh, D) * (Hq * Dh) ** (-0.5))}
    _A_in = _A_setup()

    def _B_setup():
        B, S, D, F = (1, 2048, 640, 1728)
        return {'x': _w((lambda *s: torch.randn(*s, dtype=torch.bfloat16) * 0.05)(B, S, D)), 'w_gate': _w((lambda *s: torch.randn(*s, dtype=torch.bfloat16) * 0.05)(D, F)), 'w_up': _w((lambda *s: torch.randn(*s, dtype=torch.bfloat16) * 0.05)(D, F)), 'w_down': _w((lambda *s: torch.randn(*s, dtype=torch.bfloat16) * 0.05)(F, D))}
    _B_in = _B_setup()
    return {'A_x': _A_in['x'], 'A_k_cache': _A_in['k_cache'], 'A_v_cache': _A_in['v_cache'], 'A_wq': _A_in['wq'], 'A_wo': _A_in['wo'], 'B_x': _B_in['x'], 'B_w_gate': _B_in['w_gate'], 'B_w_up': _B_in['w_up'], 'B_w_down': _B_in['w_down'], 'c': _w((lambda *s: torch.randn(*s, dtype=torch.bfloat16) * 0.1)(1, 640) * 8.0), 'w_mod': _w((lambda *s: torch.randn(*s, dtype=torch.bfloat16) * 0.1)(640, 6 * 640) * 640 ** (-0.5) * 8.0)}

def reference(A_x, A_k_cache, A_v_cache, A_wq, A_wo, B_x, B_w_gate, B_w_up, B_w_down, c, w_mod):

    def _A_ref(x, k_cache, v_cache, wq, wo):
        B, Sq, D = x.shape
        Hq, Dh = (32, 128)
        Hkv, Sk = (k_cache.shape[1], k_cache.shape[2])
        W = min(4096, max(256, Sk // 4))
        rep = Hq // Hkv
        q = (lambda x, *d: x.permute(*d))((x @ wq).reshape(B, Sq, Hq, Dh), 0, 2, 1, 3)
        k = (lambda x, n, axis: torch.repeat_interleave(x, n, dim=axis))(k_cache[:, :, Sk - W:, :], rep, axis=1)
        v = (lambda x, n, axis: torch.repeat_interleave(x, n, dim=axis))(v_cache[:, :, Sk - W:, :], rep, axis=1)
        scores = torch.einsum('bhqd,bhkd->bhqk', q, k) * Dh ** (-0.5)
        p = _softmax(scores, axis=-1)
        o = torch.einsum('bhqk,bhkd->bhqd', p, v)
        return (lambda x, *d: x.permute(*d))(o, 0, 2, 1, 3).reshape(B, Sq, Hq * Dh) @ wo

    def _B_ref(x, w_gate, w_up, w_down):
        g = _silu(x @ w_gate)
        u = x @ w_up
        return g * u @ w_down
    x = A_x
    mod = (_silu(c) @ w_mod).reshape(c.shape[0], 6, 1, -1)
    sa, ca, ga, sb, cb, gb = (mod[:, 0].clone(), mod[:, 1].clone(), mod[:, 2].clone(), mod[:, 3].clone(), mod[:, 4].clone(), mod[:, 5].clone())
    h = _layernorm(x, axis=-1) * (1 + ca) + sa
    x = x + ga * _A_ref(h, A_k_cache, A_v_cache, A_wq, A_wo)
    h = _layernorm(x, axis=-1) * (1 + cb) + sb
    x = x + gb * _B_ref(h, B_w_gate, B_w_up, B_w_down)
    return x
```

```cpp
#include <cuda_runtime.h>
#include <cuda_bf16.h>
#include <cuda.h>
#include <stdint.h>

typedef __nv_bfloat16 bf16;

constexpr int SQ = 2048, DM = 640, NH = 32, DH = 128, SK = 2048, WIN = 512, FF = 1728;
constexpr int HD = NH * DH;

__device__ float g_mod[6 * DM];
__device__ unsigned int g_cnt[256];
__device__ __align__(1024) bf16 g_h[SQ * DM];
__device__ __align__(1024) bf16 g_o[SQ * HD];
__device__ __align__(1024) bf16 g_x1[SQ * DM];
__device__ __align__(1024) bf16 g_h2[SQ * DM];
__device__ __align__(1024) bf16 g_acc[2 * SQ * DM];

#define TS(slot, i)
#define TS2(slot, i)
#define KT_BEGIN(k)
#define KT_END(k)
__device__ __forceinline__ uint32_t smem_u32(const void* p) { return (uint32_t)__cvta_generic_to_shared(p); }
__device__ __forceinline__ void mbar_init(uint32_t bar, uint32_t cnt) {
  asm volatile("mbarrier.init.shared::cta.b64 [%0], %1;" ::"r"(bar), "r"(cnt));
}
__device__ __forceinline__ void mbar_expect_tx(uint32_t bar, uint32_t bytes) {
  asm volatile("mbarrier.arrive.expect_tx.shared::cta.b64 _, [%0], %1;" ::"r"(bar), "r"(bytes) : "memory");
}
__device__ __forceinline__ void mbar_arrive(uint32_t bar) {
  asm volatile("mbarrier.arrive.shared::cta.b64 _, [%0];" ::"r"(bar) : "memory");
}
__device__ __forceinline__ void mbar_wait(uint32_t bar, uint32_t parity) {
  asm volatile(
      "{\n"
      ".reg .pred p;\n"
      "WAIT_LOOP:\n"
      "mbarrier.try_wait.parity.shared::cta.b64 p, [%0], %1;\n"
      "@p bra WAIT_DONE;\n"
      "bra WAIT_LOOP;\n"
      "WAIT_DONE:\n"
      "}\n" ::"r"(bar), "r"(parity) : "memory");
}
__device__ __forceinline__ void fence_barrier_init() { asm volatile("fence.mbarrier_init.release.cluster;" ::: "memory"); }
__device__ __forceinline__ void fence_proxy_async() { asm volatile("fence.proxy.async.shared::cta;" ::: "memory"); }
__device__ __forceinline__ void tma_2d(uint32_t dst, const CUtensorMap* m, uint32_t bar, int c0, int c1) {
  asm volatile("cp.async.bulk.tensor.2d.shared::cluster.global.mbarrier::complete_tx::bytes [%0], [%1, {%3, %4}], [%2];"
               ::"r"(dst), "l"(m), "r"(bar), "r"(c0), "r"(c1) : "memory");
}
__device__ __forceinline__ void tma_3d(uint32_t dst, const CUtensorMap* m, uint32_t bar, int c0, int c1, int c2) {
  asm volatile("cp.async.bulk.tensor.3d.shared::cluster.global.mbarrier::complete_tx::bytes [%0], [%1, {%3, %4, %5}], [%2];"
               ::"r"(dst), "l"(m), "r"(bar), "r"(c0), "r"(c1), "r"(c2) : "memory");
}
__device__ __forceinline__ uint64_t policy_evict_first() {
  uint64_t p;
  asm volatile("createpolicy.fractional.L2::evict_first.b64 %0, 1.0;" : "=l"(p));
  return p;
}
__device__ __forceinline__ void tma_2d_mc(uint32_t dst, const CUtensorMap* m, uint32_t bar, int c0, int c1, uint16_t mask) {
  asm volatile("cp.async.bulk.tensor.2d.shared::cluster.global.mbarrier::complete_tx::bytes.multicast::cluster.L2::cache_hint [%0], [%1, {%3, %4}], [%2], %5, %6;"
               ::"r"(dst), "l"(m), "r"(bar), "r"(c0), "r"(c1), "h"(mask), "l"(policy_evict_first()) : "memory");
}
__device__ __forceinline__ void tma_3d_mc(uint32_t dst, const CUtensorMap* m, uint32_t bar, int c0, int c1, int c2, uint16_t mask) {
  asm volatile("cp.async.bulk.tensor.3d.shared::cluster.global.mbarrier::complete_tx::bytes.multicast::cluster.L2::cache_hint [%0], [%1, {%3, %4, %5}], [%2], %6, %7;"
               ::"r"(dst), "l"(m), "r"(bar), "r"(c0), "r"(c1), "r"(c2), "h"(mask), "l"(policy_evict_first()) : "memory");
}
__device__ __forceinline__ void mbar_arrive_remote(uint32_t cluster_addr) {
  asm volatile("mbarrier.arrive.shared::cluster.b64 _, [%0];" ::"r"(cluster_addr) : "memory");
}
__device__ __forceinline__ void tma_reduce_add_2d(const CUtensorMap* m, uint32_t src, int c0, int c1) {
  asm volatile("cp.reduce.async.bulk.tensor.2d.global.shared::cta.add.tile.bulk_group [%0, {%2, %3}], [%1];"
               ::"l"(m), "r"(src), "r"(c0), "r"(c1) : "memory");
}
__device__ __forceinline__ void prefetch_tmap(const CUtensorMap* m) {
  asm volatile("prefetch.tensormap [%0];" ::"l"(m) : "memory");
}
__device__ __forceinline__ void wgmma_fence() { asm volatile("wgmma.fence.sync.aligned;" ::: "memory"); }
__device__ __forceinline__ void wgmma_commit() { asm volatile("wgmma.commit_group.sync.aligned;" ::: "memory"); }
template <int N> __device__ __forceinline__ void wgmma_wait() { asm volatile("wgmma.wait_group.sync.aligned %0;" ::"n"(N) : "memory"); }
template <int R> __device__ __forceinline__ void reg_alloc() { asm volatile("setmaxnreg.inc.sync.aligned.u32 %0;" ::"n"(R)); }
template <int R> __device__ __forceinline__ void reg_dealloc() { asm volatile("setmaxnreg.dec.sync.aligned.u32 %0;" ::"n"(R)); }

__device__ __forceinline__ uint64_t make_desc(uint32_t addr, uint32_t lbo, uint32_t sbo) {
  uint64_t d = 0;
  d |= (uint64_t)((addr & 0x3FFFF) >> 4);
  d |= (uint64_t)((lbo & 0x3FFFF) >> 4) << 16;
  d |= (uint64_t)((sbo & 0x3FFFF) >> 4) << 32;
  d |= (uint64_t)1 << 62;
  return d;
}
__device__ __forceinline__ uint64_t desc_kmajor(uint32_t addr) { return make_desc(addr, 16, 1024); }
__device__ __forceinline__ uint64_t desc_mnmajor(uint32_t addr, uint32_t group_stride) { return make_desc(addr, group_stride, 1024); }

__device__ __forceinline__ uint64_t desc_mn64(uint32_t addr, uint32_t group_stride) {
  uint64_t d = 0;
  d |= (uint64_t)((addr & 0x3FFFF) >> 4);
  d |= (uint64_t)((group_stride & 0x3FFFF) >> 4) << 16;
  d |= (uint64_t)(512 >> 4) << 32;
  d |= (uint64_t)2 << 62;
  return d;
}
__device__ __forceinline__ uint32_t cluster_ctarank() { uint32_t r; asm volatile("mov.u32 %0, %%cluster_ctarank;" : "=r"(r)); return r; }
__device__ __forceinline__ void cluster_arrive() { asm volatile("barrier.cluster.arrive.release.aligned;" ::: "memory"); }
__device__ __forceinline__ void cluster_wait() { asm volatile("barrier.cluster.wait.acquire.aligned;" ::: "memory"); }
__device__ __forceinline__ uint32_t mapa(uint32_t addr, uint32_t cta) {
  uint32_t r;
  asm volatile("mapa.shared::cluster.u32 %0, %1, %2;" : "=r"(r) : "r"(addr), "r"(cta));
  return r;
}
__device__ __forceinline__ float bf_lo(uint32_t u) { return __uint_as_float(u << 16); }
__device__ __forceinline__ float bf_hi(uint32_t u) { return __uint_as_float(u & 0xffff0000u); }
__device__ __forceinline__ uint32_t pack_bf16(float lo, float hi) {
  uint32_t r;
  asm("cvt.rn.bf16x2.f32 %0, %1, %2;" : "=r"(r) : "f"(hi), "f"(lo));
  return r;
}
__device__ __forceinline__ float bf16_round(float x) { return __bfloat162float(__float2bfloat16_rn(x)); }
__device__ __forceinline__ float ex2(float x) {
  float y;
  asm("ex2.approx.ftz.f32 %0, %1;" : "=f"(y) : "f"(x));
  return y;
}

__device__ __forceinline__ void stmatrix_x4(uint32_t addr, uint32_t r0, uint32_t r1, uint32_t r2, uint32_t r3) {
  asm volatile("stmatrix.sync.aligned.m8n8.x4.shared.b16 [%0], {%1,%2,%3,%4};" ::"r"(addr), "r"(r0), "r"(r1), "r"(r2), "r"(r3) : "memory");
}
__device__ __forceinline__ void named_bar_sync(int id, int n) { asm volatile("bar.sync %0, %1;" ::"r"(id), "r"(n) : "memory"); }
__device__ __forceinline__ void named_bar_arrive(int id, int n) { asm volatile("bar.arrive %0, %1;" ::"r"(id), "r"(n) : "memory"); }
__device__ __forceinline__ void quad_transpose(uint32_t (&r)[4], int lane) {
  const bool odd = lane & 1, hi = lane & 2;
  uint32_t s0 = odd ? r[0] : r[1], s1 = odd ? r[2] : r[3];
  s0 = __shfl_xor_sync(0xffffffffu, s0, 1); s1 = __shfl_xor_sync(0xffffffffu, s1, 1);
  if (odd) { r[0] = s0; r[2] = s1; } else { r[1] = s0; r[3] = s1; }
  uint32_t t0 = hi ? r[0] : r[2], t1 = hi ? r[1] : r[3];
  t0 = __shfl_xor_sync(0xffffffffu, t0, 2); t1 = __shfl_xor_sync(0xffffffffu, t1, 2);
  if (hi) { r[0] = t0; r[1] = t1; } else { r[2] = t0; r[3] = t1; }
}

template <int V> struct IC { static constexpr int value = V; };
struct TrueT { static constexpr bool value = true; };
struct FalseT { static constexpr bool value = false; };
__device__ __forceinline__ float rcp_approx(float x) { float y; asm("rcp.approx.ftz.f32 %0, %1;" : "=f"(y) : "f"(x)); return y; }
__device__ __forceinline__ void pdl_wait() { asm volatile("griddepcontrol.wait;" ::: "memory"); }
__device__ __forceinline__ void pdl_launch() { asm volatile("griddepcontrol.launch_dependents;" ::: "memory"); }
__device__ __forceinline__ void vfma(float& d, float a, float b, float c) { asm volatile("fma.rn.f32 %0, %1, %2, %3;" : "=f"(d) : "f"(a), "f"(b), "f"(c)); }
__device__ __forceinline__ void vex2(float& x) { asm volatile("ex2.approx.ftz.f32 %0, %0;" : "+f"(x)); }
__device__ __forceinline__ void vadd(float& d, float a) { asm volatile("add.f32 %0, %0, %1;" : "+f"(d) : "f"(a)); }
__device__ __forceinline__ void vmul(float& d, float a) { asm volatile("mul.f32 %0, %0, %1;" : "+f"(d) : "f"(a)); }
__device__ __forceinline__ uint32_t vpack(float lo, float hi) { uint32_t r; asm volatile("cvt.rn.bf16x2.f32 %0, %1, %2;" : "=r"(r) : "f"(hi), "f"(lo)); return r; }
__device__ __forceinline__ void wgmma_rs_n128_t1(float (&d)[64], uint32_t a0, uint32_t a1, uint32_t a2, uint32_t a3, uint64_t db, int sc) {
  asm volatile("{\n.reg .pred p;\nsetp.ne.b32 p, %69, 0;\n"
    "wgmma.mma_async.sync.aligned.m64n128k16.f32.bf16.bf16 "
    "{%0, %1, %2, %3, %4, %5, %6, %7, %8, %9, %10, %11, %12, %13, %14, %15, %16, %17, %18, %19, %20, %21, %22, %23, %24, %25, %26, %27, %28, %29, %30, %31, %32, %33, %34, %35, %36, %37, %38, %39, %40, %41, %42, %43, %44, %45, %46, %47, %48, %49, %50, %51, %52, %53, %54, %55, %56, %57, %58, %59, %60, %61, %62, %63}, {%64, %65, %66, %67}, %68, p, 1, 1, 1;\n}\n"
    : "+f"(d[0]), "+f"(d[1]), "+f"(d[2]), "+f"(d[3]), "+f"(d[4]), "+f"(d[5]), "+f"(d[6]), "+f"(d[7]), "+f"(d[8]), "+f"(d[9]), "+f"(d[10]), "+f"(d[11]), "+f"(d[12]), "+f"(d[13]), "+f"(d[14]), "+f"(d[15]), "+f"(d[16]), "+f"(d[17]), "+f"(d[18]), "+f"(d[19]), "+f"(d[20]), "+f"(d[21]), "+f"(d[22]), "+f"(d[23]), "+f"(d[24]), "+f"(d[25]), "+f"(d[26]), "+f"(d[27]), "+f"(d[28]), "+f"(d[29]), "+f"(d[30]), "+f"(d[31]), "+f"(d[32]), "+f"(d[33]), "+f"(d[34]), "+f"(d[35]), "+f"(d[36]), "+f"(d[37]), "+f"(d[38]), "+f"(d[39]), "+f"(d[40]), "+f"(d[41]), "+f"(d[42]), "+f"(d[43]), "+f"(d[44]), "+f"(d[45]), "+f"(d[46]), "+f"(d[47]), "+f"(d[48]), "+f"(d[49]), "+f"(d[50]), "+f"(d[51]), "+f"(d[52]), "+f"(d[53]), "+f"(d[54]), "+f"(d[55]), "+f"(d[56]), "+f"(d[57]), "+f"(d[58]), "+f"(d[59]), "+f"(d[60]), "+f"(d[61]), "+f"(d[62]), "+f"(d[63])
    : "r"(a0), "r"(a1), "r"(a2), "r"(a3), "l"(db), "r"(sc));
}

__device__ __forceinline__ void wgmma_ss_n128_t0(float (&d)[64], uint64_t da, uint64_t db, int sc) {
  asm volatile("{\n.reg .pred p;\nsetp.ne.b32 p, %66, 0;\n"
    "wgmma.mma_async.sync.aligned.m64n128k16.f32.bf16.bf16 "
    "{%0, %1, %2, %3, %4, %5, %6, %7, %8, %9, %10, %11, %12, %13, %14, %15, %16, %17, %18, %19, %20, %21, %22, %23, %24, %25, %26, %27, %28, %29, %30, %31, %32, %33, %34, %35, %36, %37, %38, %39, %40, %41, %42, %43, %44, %45, %46, %47, %48, %49, %50, %51, %52, %53, %54, %55, %56, %57, %58, %59, %60, %61, %62, %63}, %64, %65, p, 1, 1, 0, 0;\n}\n"
    : "+f"(d[0]), "+f"(d[1]), "+f"(d[2]), "+f"(d[3]), "+f"(d[4]), "+f"(d[5]), "+f"(d[6]), "+f"(d[7]), "+f"(d[8]), "+f"(d[9]), "+f"(d[10]), "+f"(d[11]), "+f"(d[12]), "+f"(d[13]), "+f"(d[14]), "+f"(d[15]), "+f"(d[16]), "+f"(d[17]), "+f"(d[18]), "+f"(d[19]), "+f"(d[20]), "+f"(d[21]), "+f"(d[22]), "+f"(d[23]), "+f"(d[24]), "+f"(d[25]), "+f"(d[26]), "+f"(d[27]), "+f"(d[28]), "+f"(d[29]), "+f"(d[30]), "+f"(d[31]), "+f"(d[32]), "+f"(d[33]), "+f"(d[34]), "+f"(d[35]), "+f"(d[36]), "+f"(d[37]), "+f"(d[38]), "+f"(d[39]), "+f"(d[40]), "+f"(d[41]), "+f"(d[42]), "+f"(d[43]), "+f"(d[44]), "+f"(d[45]), "+f"(d[46]), "+f"(d[47]), "+f"(d[48]), "+f"(d[49]), "+f"(d[50]), "+f"(d[51]), "+f"(d[52]), "+f"(d[53]), "+f"(d[54]), "+f"(d[55]), "+f"(d[56]), "+f"(d[57]), "+f"(d[58]), "+f"(d[59]), "+f"(d[60]), "+f"(d[61]), "+f"(d[62]), "+f"(d[63])
    : "l"(da), "l"(db), "r"(sc));
}

__device__ __forceinline__ void wgmma_ss_n128_t0_z(float (&d)[64], uint64_t da, uint64_t db) {
  asm volatile("{\n.reg .pred p;\nsetp.eq.u32 p, 1, 0;\n"
    "wgmma.mma_async.sync.aligned.m64n128k16.f32.bf16.bf16 "
    "{%0, %1, %2, %3, %4, %5, %6, %7, %8, %9, %10, %11, %12, %13, %14, %15, %16, %17, %18, %19, %20, %21, %22, %23, %24, %25, %26, %27, %28, %29, %30, %31, %32, %33, %34, %35, %36, %37, %38, %39, %40, %41, %42, %43, %44, %45, %46, %47, %48, %49, %50, %51, %52, %53, %54, %55, %56, %57, %58, %59, %60, %61, %62, %63}, %64, %65, p, 1, 1, 0, 0;\n}\n"
    : "=f"(d[0]), "=f"(d[1]), "=f"(d[2]), "=f"(d[3]), "=f"(d[4]), "=f"(d[5]), "=f"(d[6]), "=f"(d[7]), "=f"(d[8]), "=f"(d[9]), "=f"(d[10]), "=f"(d[11]), "=f"(d[12]), "=f"(d[13]), "=f"(d[14]), "=f"(d[15]), "=f"(d[16]), "=f"(d[17]), "=f"(d[18]), "=f"(d[19]), "=f"(d[20]), "=f"(d[21]), "=f"(d[22]), "=f"(d[23]), "=f"(d[24]), "=f"(d[25]), "=f"(d[26]), "=f"(d[27]), "=f"(d[28]), "=f"(d[29]), "=f"(d[30]), "=f"(d[31]), "=f"(d[32]), "=f"(d[33]), "=f"(d[34]), "=f"(d[35]), "=f"(d[36]), "=f"(d[37]), "=f"(d[38]), "=f"(d[39]), "=f"(d[40]), "=f"(d[41]), "=f"(d[42]), "=f"(d[43]), "=f"(d[44]), "=f"(d[45]), "=f"(d[46]), "=f"(d[47]), "=f"(d[48]), "=f"(d[49]), "=f"(d[50]), "=f"(d[51]), "=f"(d[52]), "=f"(d[53]), "=f"(d[54]), "=f"(d[55]), "=f"(d[56]), "=f"(d[57]), "=f"(d[58]), "=f"(d[59]), "=f"(d[60]), "=f"(d[61]), "=f"(d[62]), "=f"(d[63])
    : "l"(da), "l"(db));
}

__device__ __forceinline__ void wgmma_ss_n128_t1(float (&d)[64], uint64_t da, uint64_t db, int sc) {
  asm volatile("{\n.reg .pred p;\nsetp.ne.b32 p, %66, 0;\n"
    "wgmma.mma_async.sync.aligned.m64n128k16.f32.bf16.bf16 "
    "{%0, %1, %2, %3, %4, %5, %6, %7, %8, %9, %10, %11, %12, %13, %14, %15, %16, %17, %18, %19, %20, %21, %22, %23, %24, %25, %26, %27, %28, %29, %30, %31, %32, %33, %34, %35, %36, %37, %38, %39, %40, %41, %42, %43, %44, %45, %46, %47, %48, %49, %50, %51, %52, %53, %54, %55, %56, %57, %58, %59, %60, %61, %62, %63}, %64, %65, p, 1, 1, 0, 1;\n}\n"
    : "+f"(d[0]), "+f"(d[1]), "+f"(d[2]), "+f"(d[3]), "+f"(d[4]), "+f"(d[5]), "+f"(d[6]), "+f"(d[7]), "+f"(d[8]), "+f"(d[9]), "+f"(d[10]), "+f"(d[11]), "+f"(d[12]), "+f"(d[13]), "+f"(d[14]), "+f"(d[15]), "+f"(d[16]), "+f"(d[17]), "+f"(d[18]), "+f"(d[19]), "+f"(d[20]), "+f"(d[21]), "+f"(d[22]), "+f"(d[23]), "+f"(d[24]), "+f"(d[25]), "+f"(d[26]), "+f"(d[27]), "+f"(d[28]), "+f"(d[29]), "+f"(d[30]), "+f"(d[31]), "+f"(d[32]), "+f"(d[33]), "+f"(d[34]), "+f"(d[35]), "+f"(d[36]), "+f"(d[37]), "+f"(d[38]), "+f"(d[39]), "+f"(d[40]), "+f"(d[41]), "+f"(d[42]), "+f"(d[43]), "+f"(d[44]), "+f"(d[45]), "+f"(d[46]), "+f"(d[47]), "+f"(d[48]), "+f"(d[49]), "+f"(d[50]), "+f"(d[51]), "+f"(d[52]), "+f"(d[53]), "+f"(d[54]), "+f"(d[55]), "+f"(d[56]), "+f"(d[57]), "+f"(d[58]), "+f"(d[59]), "+f"(d[60]), "+f"(d[61]), "+f"(d[62]), "+f"(d[63])
    : "l"(da), "l"(db), "r"(sc));
}

__device__ __forceinline__ void wgmma_ss_n192_t1(float (&d)[96], uint64_t da, uint64_t db, int sc) {
  asm volatile("{\n.reg .pred p;\nsetp.ne.b32 p, %98, 0;\n"
    "wgmma.mma_async.sync.aligned.m64n192k16.f32.bf16.bf16 "
    "{%0, %1, %2, %3, %4, %5, %6, %7, %8, %9, %10, %11, %12, %13, %14, %15, %16, %17, %18, %19, %20, %21, %22, %23, %24, %25, %26, %27, %28, %29, %30, %31, %32, %33, %34, %35, %36, %37, %38, %39, %40, %41, %42, %43, %44, %45, %46, %47, %48, %49, %50, %51, %52, %53, %54, %55, %56, %57, %58, %59, %60, %61, %62, %63, %64, %65, %66, %67, %68, %69, %70, %71, %72, %73, %74, %75, %76, %77, %78, %79, %80, %81, %82, %83, %84, %85, %86, %87, %88, %89, %90, %91, %92, %93, %94, %95}, %96, %97, p, 1, 1, 0, 1;\n}\n"
    : "+f"(d[0]), "+f"(d[1]), "+f"(d[2]), "+f"(d[3]), "+f"(d[4]), "+f"(d[5]), "+f"(d[6]), "+f"(d[7]), "+f"(d[8]), "+f"(d[9]), "+f"(d[10]), "+f"(d[11]), "+f"(d[12]), "+f"(d[13]), "+f"(d[14]), "+f"(d[15]), "+f"(d[16]), "+f"(d[17]), "+f"(d[18]), "+f"(d[19]), "+f"(d[20]), "+f"(d[21]), "+f"(d[22]), "+f"(d[23]), "+f"(d[24]), "+f"(d[25]), "+f"(d[26]), "+f"(d[27]), "+f"(d[28]), "+f"(d[29]), "+f"(d[30]), "+f"(d[31]), "+f"(d[32]), "+f"(d[33]), "+f"(d[34]), "+f"(d[35]), "+f"(d[36]), "+f"(d[37]), "+f"(d[38]), "+f"(d[39]), "+f"(d[40]), "+f"(d[41]), "+f"(d[42]), "+f"(d[43]), "+f"(d[44]), "+f"(d[45]), "+f"(d[46]), "+f"(d[47]), "+f"(d[48]), "+f"(d[49]), "+f"(d[50]), "+f"(d[51]), "+f"(d[52]), "+f"(d[53]), "+f"(d[54]), "+f"(d[55]), "+f"(d[56]), "+f"(d[57]), "+f"(d[58]), "+f"(d[59]), "+f"(d[60]), "+f"(d[61]), "+f"(d[62]), "+f"(d[63]), "+f"(d[64]), "+f"(d[65]), "+f"(d[66]), "+f"(d[67]), "+f"(d[68]), "+f"(d[69]), "+f"(d[70]), "+f"(d[71]), "+f"(d[72]), "+f"(d[73]), "+f"(d[74]), "+f"(d[75]), "+f"(d[76]), "+f"(d[77]), "+f"(d[78]), "+f"(d[79]), "+f"(d[80]), "+f"(d[81]), "+f"(d[82]), "+f"(d[83]), "+f"(d[84]), "+f"(d[85]), "+f"(d[86]), "+f"(d[87]), "+f"(d[88]), "+f"(d[89]), "+f"(d[90]), "+f"(d[91]), "+f"(d[92]), "+f"(d[93]), "+f"(d[94]), "+f"(d[95])
    : "l"(da), "l"(db), "r"(sc));
}

__device__ __forceinline__ void wgmma_ss_n256_t1(float (&d)[128], uint64_t da, uint64_t db, int sc) {
  asm volatile("{\n.reg .pred p;\nsetp.ne.b32 p, %130, 0;\n"
    "wgmma.mma_async.sync.aligned.m64n256k16.f32.bf16.bf16 "
    "{%0, %1, %2, %3, %4, %5, %6, %7, %8, %9, %10, %11, %12, %13, %14, %15, %16, %17, %18, %19, %20, %21, %22, %23, %24, %25, %26, %27, %28, %29, %30, %31, %32, %33, %34, %35, %36, %37, %38, %39, %40, %41, %42, %43, %44, %45, %46, %47, %48, %49, %50, %51, %52, %53, %54, %55, %56, %57, %58, %59, %60, %61, %62, %63, %64, %65, %66, %67, %68, %69, %70, %71, %72, %73, %74, %75, %76, %77, %78, %79, %80, %81, %82, %83, %84, %85, %86, %87, %88, %89, %90, %91, %92, %93, %94, %95, %96, %97, %98, %99, %100, %101, %102, %103, %104, %105, %106, %107, %108, %109, %110, %111, %112, %113, %114, %115, %116, %117, %118, %119, %120, %121, %122, %123, %124, %125, %126, %127}, %128, %129, p, 1, 1, 0, 1;\n}\n"
    : "+f"(d[0]), "+f"(d[1]), "+f"(d[2]), "+f"(d[3]), "+f"(d[4]), "+f"(d[5]), "+f"(d[6]), "+f"(d[7]), "+f"(d[8]), "+f"(d[9]), "+f"(d[10]), "+f"(d[11]), "+f"(d[12]), "+f"(d[13]), "+f"(d[14]), "+f"(d[15]), "+f"(d[16]), "+f"(d[17]), "+f"(d[18]), "+f"(d[19]), "+f"(d[20]), "+f"(d[21]), "+f"(d[22]), "+f"(d[23]), "+f"(d[24]), "+f"(d[25]), "+f"(d[26]), "+f"(d[27]), "+f"(d[28]), "+f"(d[29]), "+f"(d[30]), "+f"(d[31]), "+f"(d[32]), "+f"(d[33]), "+f"(d[34]), "+f"(d[35]), "+f"(d[36]), "+f"(d[37]), "+f"(d[38]), "+f"(d[39]), "+f"(d[40]), "+f"(d[41]), "+f"(d[42]), "+f"(d[43]), "+f"(d[44]), "+f"(d[45]), "+f"(d[46]), "+f"(d[47]), "+f"(d[48]), "+f"(d[49]), "+f"(d[50]), "+f"(d[51]), "+f"(d[52]), "+f"(d[53]), "+f"(d[54]), "+f"(d[55]), "+f"(d[56]), "+f"(d[57]), "+f"(d[58]), "+f"(d[59]), "+f"(d[60]), "+f"(d[61]), "+f"(d[62]), "+f"(d[63]), "+f"(d[64]), "+f"(d[65]), "+f"(d[66]), "+f"(d[67]), "+f"(d[68]), "+f"(d[69]), "+f"(d[70]), "+f"(d[71]), "+f"(d[72]), "+f"(d[73]), "+f"(d[74]), "+f"(d[75]), "+f"(d[76]), "+f"(d[77]), "+f"(d[78]), "+f"(d[79]), "+f"(d[80]), "+f"(d[81]), "+f"(d[82]), "+f"(d[83]), "+f"(d[84]), "+f"(d[85]), "+f"(d[86]), "+f"(d[87]), "+f"(d[88]), "+f"(d[89]), "+f"(d[90]), "+f"(d[91]), "+f"(d[92]), "+f"(d[93]), "+f"(d[94]), "+f"(d[95]), "+f"(d[96]), "+f"(d[97]), "+f"(d[98]), "+f"(d[99]), "+f"(d[100]), "+f"(d[101]), "+f"(d[102]), "+f"(d[103]), "+f"(d[104]), "+f"(d[105]), "+f"(d[106]), "+f"(d[107]), "+f"(d[108]), "+f"(d[109]), "+f"(d[110]), "+f"(d[111]), "+f"(d[112]), "+f"(d[113]), "+f"(d[114]), "+f"(d[115]), "+f"(d[116]), "+f"(d[117]), "+f"(d[118]), "+f"(d[119]), "+f"(d[120]), "+f"(d[121]), "+f"(d[122]), "+f"(d[123]), "+f"(d[124]), "+f"(d[125]), "+f"(d[126]), "+f"(d[127])
    : "l"(da), "l"(db), "r"(sc));
}

template <int R> __device__ __forceinline__ void fence_regs(float (&d)[R]) {
#pragma unroll
  for (int i = 0; i < R; i++) asm volatile("" : "+f"(d[i])::"memory");
}

__global__ void __launch_bounds__(256) mod_kernel(const bf16* __restrict__ c, const bf16* __restrict__ w_mod) {
  __shared__ float red[8][32];
  KT_BEGIN(0);
  pdl_launch();
  if (blockIdx.x == 0) g_cnt[threadIdx.x] = 0;
  const int t = threadIdx.x, cq = t & 3, rg = t >> 2;
  const int col0 = blockIdx.x * 32 + cq * 8;
  uint4 w[10];
#pragma unroll
  for (int i = 0; i < 10; i++) w[i] = __ldg((const uint4*)(w_mod + (size_t)(rg + 64 * i) * (6 * DM) + col0));
  float acc[8];
#pragma unroll
  for (int j = 0; j < 8; j++) acc[j] = 0.f;
#pragma unroll
  for (int i = 0; i < 10; i++) {
    float cv = __bfloat162float(c[rg + 64 * i]);
    float s = bf16_round(cv * rcp_approx(1.f + ex2(-1.4426950408889634f * cv)));
    const __nv_bfloat162* p = (const __nv_bfloat162*)&w[i];
#pragma unroll
    for (int j = 0; j < 4; j++) {
      float2 f = __bfloat1622float2(p[j]);
      acc[2 * j] += s * f.x;
      acc[2 * j + 1] += s * f.y;
    }
  }
#pragma unroll
  for (int j = 0; j < 8; j++) {
    acc[j] += __shfl_xor_sync(0xffffffffu, acc[j], 4);
    acc[j] += __shfl_xor_sync(0xffffffffu, acc[j], 8);
    acc[j] += __shfl_xor_sync(0xffffffffu, acc[j], 16);
  }
  if ((t & 31) < 4) {
#pragma unroll
    for (int j = 0; j < 8; j++) red[t >> 5][cq * 8 + j] = acc[j];
  }
  __syncthreads();
  if (t < 32) {
    float s = 0.f;
#pragma unroll
    for (int w8 = 0; w8 < 8; w8++) s += red[w8][t];
    g_mod[blockIdx.x * 32 + t] = bf16_round(s);
  }
  KT_END(0);
}

__global__ void __launch_bounds__(256) ln_kernel(const bf16* __restrict__ x, bf16* __restrict__ out, int shift_idx, int scale_idx) {
  const int warp = threadIdx.x >> 5, lane = threadIdx.x & 31;
  const int row = blockIdx.x * 8 + warp;
  KT_BEGIN(1);
  pdl_launch();
#pragma unroll
  for (int i = 0; i < 5; i++) {
    *(uint2*)(g_acc + (size_t)row * DM + i * 128 + lane * 4) = make_uint2(0u, 0u);
    *(uint2*)(g_acc + (size_t)(SQ + row) * DM + i * 128 + lane * 4) = make_uint2(0u, 0u);
  }
  const bf16* xr = x + (size_t)row * DM;
  float v[20];
#pragma unroll
  for (int i = 0; i < 5; i++) {
    uint2 u = *(const uint2*)(xr + i * 128 + lane * 4);
    float2 a = __bfloat1622float2(*(__nv_bfloat162*)&u.x), b = __bfloat1622float2(*(__nv_bfloat162*)&u.y);
    v[4 * i] = a.x; v[4 * i + 1] = a.y; v[4 * i + 2] = b.x; v[4 * i + 3] = b.y;
  }
  float s = 0.f;
#pragma unroll
  for (int i = 0; i < 20; i++) s += v[i];
#pragma unroll
  for (int o = 16; o > 0; o >>= 1) s += __shfl_xor_sync(0xffffffffu, s, o);
  const float mean = s * (1.f / DM);
  float q = 0.f;
#pragma unroll
  for (int i = 0; i < 20; i++) { float d = v[i] - mean; q += d * d; }
#pragma unroll
  for (int o = 16; o > 0; o >>= 1) q += __shfl_xor_sync(0xffffffffu, q, o);
  const float rstd = rsqrtf(q * (1.f / DM) + 1e-5f);
  pdl_wait();
  const float* sh = g_mod + shift_idx * DM;
  const float* sc = g_mod + scale_idx * DM;
#pragma unroll
  for (int i = 0; i < 5; i++) {
    int c = i * 128 + lane * 4;
    float4 a = *(const float4*)(sc + c), b = *(const float4*)(sh + c);
    float h0 = (v[4 * i] - mean) * rstd * (1.f + a.x) + b.x;
    float h1 = (v[4 * i + 1] - mean) * rstd * (1.f + a.y) + b.y;
    float h2 = (v[4 * i + 2] - mean) * rstd * (1.f + a.z) + b.z;
    float h3 = (v[4 * i + 3] - mean) * rstd * (1.f + a.w) + b.w;
    uint2 u; u.x = pack_bf16(h0, h1); u.y = pack_bf16(h2, h3);
    *(uint2*)(out + (size_t)row * DM + c) = u;
  }
  KT_END(1);
}

template <int MODE>
__device__ __forceinline__ void signal_done(const int mt) {
  asm volatile("fence.proxy.async;" ::: "memory");
  __threadfence();
  atomicAdd(&g_cnt[MODE * 16 + mt], 1u);
}
template <int MODE>
__device__ __forceinline__ void finish_row(const bf16* __restrict__ accr, const bf16* __restrict__ resr, bf16* __restrict__ yout,
                                           bf16* __restrict__ hout, const int lane) {
  float v[20];
  uint2 ua[5], ur[5];
  float4 g[5], a[5], b[5];
#pragma unroll
  for (int i = 0; i < 5; i++) {
    const int c = i * 128 + lane * 4;
    asm volatile("ld.relaxed.gpu.global.v2.u32 {%0,%1}, [%2];" : "=r"(ua[i].x), "=r"(ua[i].y) : "l"(accr + c) : "memory");
    ur[i] = *(const uint2*)(resr + c);
    g[i] = *(const float4*)(g_mod + (MODE == 0 ? 2 : 5) * DM + c);
    if (MODE == 0) { a[i] = *(const float4*)(g_mod + 4 * DM + c); b[i] = *(const float4*)(g_mod + 3 * DM + c); }
  }
#pragma unroll
  for (int i = 0; i < 5; i++) {
    const uint32_t t0 = pack_bf16(g[i].x * bf_lo(ua[i].x), g[i].y * bf_hi(ua[i].x)), t1 = pack_bf16(g[i].z * bf_lo(ua[i].y), g[i].w * bf_hi(ua[i].y));
    uint2 y;
    y.x = pack_bf16(bf_lo(ur[i].x) + bf_lo(t0), bf_hi(ur[i].x) + bf_hi(t0));
    y.y = pack_bf16(bf_lo(ur[i].y) + bf_lo(t1), bf_hi(ur[i].y) + bf_hi(t1));
    *(uint2*)(yout + i * 128 + lane * 4) = y;
    v[4 * i] = bf_lo(y.x); v[4 * i + 1] = bf_hi(y.x); v[4 * i + 2] = bf_lo(y.y); v[4 * i + 3] = bf_hi(y.y);
  }
  if (MODE == 0) {
    float s = 0.f;
#pragma unroll
    for (int i = 0; i < 20; i++) s += v[i];
#pragma unroll
    for (int o = 16; o > 0; o >>= 1) s += __shfl_xor_sync(0xffffffffu, s, o);
    const float mean = s * (1.f / DM);
    float q = 0.f;
#pragma unroll
    for (int i = 0; i < 20; i++) { float d = v[i] - mean; q += d * d; }
#pragma unroll
    for (int o = 16; o > 0; o >>= 1) q += __shfl_xor_sync(0xffffffffu, q, o);
    const float rstd = rsqrtf(q * (1.f / DM) + 1e-5f);
#pragma unroll
    for (int i = 0; i < 5; i++) {
      uint2 w;
      w.x = pack_bf16((v[4 * i] - mean) * rstd * (1.f + a[i].x) + b[i].x, (v[4 * i + 1] - mean) * rstd * (1.f + a[i].y) + b[i].y);
      w.y = pack_bf16((v[4 * i + 2] - mean) * rstd * (1.f + a[i].z) + b[i].z, (v[4 * i + 3] - mean) * rstd * (1.f + a[i].w) + b[i].w);
      *(uint2*)(hout + i * 128 + lane * 4) = w;
    }
  }
}
template <int MODE>
__device__ __forceinline__ void group_finish(const int mt, const int slice, const int ctid, const bf16* __restrict__ acc,
                                             const bf16* __restrict__ res, bf16* __restrict__ out) {
  if (ctid == 0) {
    const unsigned int* cnt = &g_cnt[MODE * 16 + mt];
    unsigned int v;
    int spins = 0;
    do {
      asm volatile("ld.acquire.gpu.global.u32 %0, [%1];" : "=r"(v) : "l"(cnt) : "memory");
    } while (v < 16u && ++spins < (1 << 24));
  }
  named_bar_sync(5, 256);
  const int w = ctid >> 5, lane = ctid & 31;
#pragma unroll 1
  for (int r = 0; r < 2; r++) {
    const size_t row = mt * 128 + slice * 16 + w * 2 + r;
    finish_row<MODE>(acc + row * DM, res + row * DM, out + row * DM, g_h2 + row * DM, lane);
  }
}

constexpr int A_NS = 10;
constexpr int A_NB = 14;
constexpr int SLOT = 16384;
constexpr int A_SMEM = A_NS * SLOT + 65536 + 1024 + 512;

__device__ __forceinline__ uint32_t oproj_slot(uint32_t i) { return (uint32_t)((0xdcba76541098ull >> (4 * i)) & 15); }

__global__ void __cluster_dims__(2, 1, 1) __launch_bounds__(384, 1)
attn_kernel(const __grid_constant__ CUtensorMap tm_h, const __grid_constant__ CUtensorMap tm_wq,
            const __grid_constant__ CUtensorMap tm_k, const __grid_constant__ CUtensorMap tm_v,
            const __grid_constant__ CUtensorMap tm_o, const __grid_constant__ CUtensorMap tm_wo,
            const __grid_constant__ CUtensorMap tm_part, const bf16* __restrict__ xres) {
  extern __shared__ uint8_t smem_raw[];
  const uint32_t sbase = (smem_u32(smem_raw) + 1023) & ~1023u;
  const uint32_t s_ring = sbase;
  const uint32_t s_q = sbase + A_NS * SLOT;
  const uint32_t s_bar = s_q + 65536;
  const uint32_t b_oready = s_bar + 8 * (2 * A_NB);
  const int tid = threadIdx.x, wg = tid >> 7, warp = tid >> 5, lane = tid & 31;
  const int mt = blockIdx.x & 15, hg = blockIdx.x >> 4;
  KT_BEGIN(2);
  pdl_launch();

  if (tid == 0) {
    for (int i = 0; i < A_NB; i++) { mbar_init(s_bar + 8 * i, 1); mbar_init(s_bar + 8 * (A_NB + i), 16); }
    mbar_init(b_oready, 8);
    fence_barrier_init();
  }
  __syncthreads();
  cluster_arrive(); cluster_wait();
  const uint32_t rank = cluster_ctarank();

  if (wg == 0) {
    reg_dealloc<24>();
    if (tid == 0) {
      uint32_t sl = 0, eph = 0x3ffu;
      auto wait_empty = [&](uint32_t slot) {
        mbar_wait(s_bar + 8 * (A_NB + slot), (eph >> slot) & 1);
        eph ^= 1u << slot;
      };
      auto acquire = [&](uint32_t& slot_addr, uint32_t& bar) {
        wait_empty(sl);
        bar = s_bar + 8 * sl;
        slot_addr = s_ring + sl * SLOT;
        mbar_expect_tx(bar, SLOT);
        if (++sl == A_NS) sl = 0;
      };
      auto acquire2 = [&](uint32_t& slot_addr, uint32_t& bar) {
        bar = s_bar + 8 * sl;
        wait_empty(sl);
        const uint32_t s1 = s_ring + sl * SLOT;
        if (++sl == A_NS) sl = 0;
        wait_empty(sl);
        slot_addr = s_ring + sl * SLOT;
        if (++sl == A_NS) sl = 0;
        mbar_expect_tx(bar, 2 * SLOT);
        return s1;
      };
      pdl_wait();
      for (int p = 0; p < 2; p++) {
        const int head0 = hg * 4 + p * 2;
        for (int k = 0; k < 10; k++) {
          uint32_t a, b;
          const bool bfirst = (sl == A_NS - 2);
          if (!bfirst) { acquire(a, b); tma_2d(a, &tm_h, b, k * 64, mt * 128); }
          const uint32_t a1 = acquire2(a, b);
          tma_3d_mc(a1 + rank * 8192, &tm_wq, b, 0, k * 64, head0 * 2 + rank, 3);
          tma_3d_mc(a + rank * 8192, &tm_wq, b, 0, k * 64, head0 * 2 + 2 + rank, 3);
          if (bfirst) { acquire(a, b); tma_2d(a, &tm_h, b, k * 64, mt * 128); }
        }
        for (int t = 0; t <= 8; t++) {
          uint32_t a, b;
          if (t < 8) {
            const int row0 = (head0 + (t >> 2)) * SK + (SK - WIN) + (t & 3) * 128;
            const uint32_t a1 = acquire2(a, b);
            tma_2d_mc(a1 + rank * 8192, &tm_k, b, 0, row0 + rank * 64, 3);
            tma_2d_mc(a + rank * 8192, &tm_k, b, 64, row0 + rank * 64, 3);
          }
          if (t > 0) {
            const int row0 = (head0 + ((t - 1) >> 2)) * SK + (SK - WIN) + ((t - 1) & 3) * 128;
            const uint32_t a1 = acquire2(a, b);
            tma_3d_mc(a1 + rank * 8192, &tm_v, b, 0, row0, rank, 3);
            tma_3d_mc(a + rank * 8192, &tm_v, b, 0, row0 + 64, rank, 3);
          }
        }
      }
      {
        for (int j = 0; j < 4; j++) wait_empty(4 + j);
        mbar_wait(b_oready, 0);
        mbar_expect_tx(s_bar + 8 * 4, 4 * SLOT);
        for (int j = 0; j < 4; j++) tma_2d(s_ring + (4 + j) * SLOT, &tm_o, s_bar + 8 * 4, hg * 512 + j * 64, mt * 128);
        uint32_t bi = 0;
        for (int c = 0; c < 5; c++) {
          for (int k = 0; k < 8; k++) {
            const uint32_t slot = oproj_slot(bi);
            wait_empty(slot);
            const uint32_t bar = s_bar + 8 * slot, dst = s_ring + slot * SLOT;
            mbar_expect_tx(bar, SLOT);
            tma_3d_mc(dst + rank * 8192, &tm_wo, bar, 0, hg * 512 + k * 64, c * 2 + rank, 3);
            if (++bi == 12) bi = 0;
          }
        }
      }
    }
  } else {
    reg_alloc<240>();
    const int cw = wg - 1;
    const uint32_t r_bar = mapa(s_bar, rank ^ 1);
    uint32_t sl = 0, fph = 0;
    uint32_t rl = 0;
    auto wait_next = [&]() -> uint32_t {
      mbar_wait(s_bar + 8 * sl, (fph >> sl) & 1);
      fph ^= 1u << sl;
      uint32_t a = s_ring + sl * SLOT;
      if (++sl == A_NS) sl = 0;
      return a;
    };
    auto wait_next2 = [&](uint32_t& second) -> uint32_t {
      uint32_t a = wait_next();
      second = s_ring + sl * SLOT;
      if (++sl == A_NS) sl = 0;
      return a;
    };
    auto release_next = [&]() {
      if (lane == 0) { mbar_arrive(s_bar + 8 * (A_NB + rl)); mbar_arrive_remote(r_bar + 8 * (A_NB + rl)); }
      if (++rl == A_NS) rl = 0;
    };
    const float sc2 = 0.08838834764831845f * 1.4426950408889634f;
    TS(wg, 0);

#pragma unroll 1
    for (int p = 0; p < 2; p++) {
      {
        float acc[128];
#pragma unroll
        for (int i = 0; i < 128; i++) acc[i] = 0.f;
#pragma unroll 1
        for (int k = 0; k < 10; k++) {
          const bool bfirst = (sl == A_NS - 2);
          uint32_t a = 0, b0, b1;
          if (!bfirst) a = wait_next();
          b0 = wait_next2(b1);
          if (bfirst) a = wait_next();
          const uint64_t da = desc_kmajor(a + cw * 8192), db = desc_mnmajor(b0, 8192);
          wgmma_fence();
#pragma unroll
          for (int kk = 0; kk < 4; kk++) wgmma_ss_n256_t1(acc, da + kk * 2, db + kk * 128, 1);
          wgmma_commit();
          if (k > 0) { wgmma_wait<1>(); release_next(); release_next(); release_next(); }
        }
        wgmma_wait<0>();
        fence_regs(acc);
        release_next(); release_next(); release_next();
        TS(wg, 1 + p * 16);
        const int mrow = cw * 64 + (warp & 3) * 16 + ((lane >> 3) & 1) * 8 + (lane & 7);
#pragma unroll
        for (int b = 0; b < 32; b += 2) {
          const int blk = b + (lane >> 4);
          const uint32_t addr = s_q + (blk >> 3) * 16384 + mrow * 128 + (((blk & 7) ^ (lane & 7)) << 4);
          stmatrix_x4(addr, pack_bf16(acc[4 * b], acc[4 * b + 1]), pack_bf16(acc[4 * b + 2], acc[4 * b + 3]),
                      pack_bf16(acc[4 * b + 4], acc[4 * b + 5]), pack_bf16(acc[4 * b + 6], acc[4 * b + 7]));
        }
        fence_proxy_async();
        named_bar_sync(1 + cw, 128);
      }
      float o[64], s[64], rem[32];
      uint32_t pf[32];
      float m0 = 0.f, m1 = 0.f, l0 = 0.f, l1 = 0.f, al0 = 0.f, al1 = 0.f;
#pragma unroll
      for (int i = 0; i < 64; i++) o[i] = 0.f;

      auto issue_s = [&](int head_local) {
        uint32_t kb, ka = wait_next2(kb);
        const uint64_t dq = desc_kmajor(s_q + head_local * 32768 + cw * 8192), da = desc_kmajor(ka), db = desc_kmajor(kb);
        wgmma_fence();
        wgmma_ss_n128_t0_z(s, dq, da);
#pragma unroll
        for (int kk = 1; kk < 8; kk++)
          wgmma_ss_n128_t0(s, dq + (kk >> 2) * 1024 + (kk & 3) * 2, (kk < 4 ? da : db) + (kk & 3) * 2, 1);
        wgmma_commit();
      };
      auto part_a = [&](bool first) {
        float x0[4], x1[4];
#pragma unroll
        for (int c = 0; c < 4; c++) { x0[c] = fmaxf(s[4 * c], s[4 * c + 1]); x1[c] = fmaxf(s[4 * c + 2], s[4 * c + 3]); }
#pragma unroll
        for (int i = 4; i < 16; i++) {
          x0[i & 3] = fmaxf(x0[i & 3], fmaxf(s[4 * i], s[4 * i + 1]));
          x1[i & 3] = fmaxf(x1[i & 3], fmaxf(s[4 * i + 2], s[4 * i + 3]));
        }
        float n0 = fmaxf(fmaxf(x0[0], x0[1]), fmaxf(x0[2], x0[3])), n1 = fmaxf(fmaxf(x1[0], x1[1]), fmaxf(x1[2], x1[3]));
        if (!first) { n0 = fmaxf(n0, m0); n1 = fmaxf(n1, m1); }
        n0 = fmaxf(n0, __shfl_xor_sync(0xffffffffu, n0, 1)); n1 = fmaxf(n1, __shfl_xor_sync(0xffffffffu, n1, 1));
        n0 = fmaxf(n0, __shfl_xor_sync(0xffffffffu, n0, 2)); n1 = fmaxf(n1, __shfl_xor_sync(0xffffffffu, n1, 2));
        al0 = first ? 0.f : ex2((m0 - n0) * sc2); al1 = first ? 0.f : ex2((m1 - n1) * sc2);
        m0 = n0; m1 = n1;
        const float mc0 = m0 * sc2, mc1 = m1 * sc2;
#pragma unroll
        for (int i = 0; i < 8; i++) {
          asm volatile("fma.rn.f32 %0, %1, %2, %3;" : "=f"(rem[4 * i]) : "f"(s[32 + 4 * i]), "f"(sc2), "f"(-mc0));
          asm volatile("fma.rn.f32 %0, %1, %2, %3;" : "=f"(rem[4 * i + 1]) : "f"(s[32 + 4 * i + 1]), "f"(sc2), "f"(-mc0));
          asm volatile("fma.rn.f32 %0, %1, %2, %3;" : "=f"(rem[4 * i + 2]) : "f"(s[32 + 4 * i + 2]), "f"(sc2), "f"(-mc1));
          asm volatile("fma.rn.f32 %0, %1, %2, %3;" : "=f"(rem[4 * i + 3]) : "f"(s[32 + 4 * i + 3]), "f"(sc2), "f"(-mc1));
        }
        float r0 = 0.f, r1 = 0.f;
#pragma unroll
        for (int i = 0; i < 8; i++) {
          s[4 * i] = ex2(fmaf(s[4 * i], sc2, -mc0)); s[4 * i + 1] = ex2(fmaf(s[4 * i + 1], sc2, -mc0));
          s[4 * i + 2] = ex2(fmaf(s[4 * i + 2], sc2, -mc1)); s[4 * i + 3] = ex2(fmaf(s[4 * i + 3], sc2, -mc1));
          r0 += s[4 * i] + s[4 * i + 1]; r1 += s[4 * i + 2] + s[4 * i + 3];
        }
        return make_float2(r0, r1);
      };
      auto pack_a = [&]() {
#pragma unroll
        for (int i = 0; i < 16; i++) {
          uint32_t v = pack_bf16(s[2 * i], s[2 * i + 1]);
          asm volatile("mov.b32 %0, %1;" : "=r"(pf[i]) : "r"(v));
        }
      };
      auto part_b = [&]() {
        float r0 = 0.f, r1 = 0.f;
#pragma unroll
        for (int i = 0; i < 8; i++) {
          rem[4 * i] = ex2(rem[4 * i]); rem[4 * i + 1] = ex2(rem[4 * i + 1]);
          rem[4 * i + 2] = ex2(rem[4 * i + 2]); rem[4 * i + 3] = ex2(rem[4 * i + 3]);
          r0 += rem[4 * i] + rem[4 * i + 1]; r1 += rem[4 * i + 2] + rem[4 * i + 3];
          const int u = 2 * i;
          o[4 * u] *= al0; o[4 * u + 1] *= al0; o[4 * u + 2] *= al1; o[4 * u + 3] *= al1;
          o[4 * u + 4] *= al0; o[4 * u + 5] *= al0; o[4 * u + 6] *= al1; o[4 * u + 7] *= al1;
          pf[16 + 2 * i] = pack_bf16(rem[4 * i], rem[4 * i + 1]); pf[16 + 2 * i + 1] = pack_bf16(rem[4 * i + 2], rem[4 * i + 3]);
        }
        l0 += r0; l1 += r1;
      };
      auto issue_pv = [&]() {
        uint32_t vb, va = wait_next2(vb);
        const uint64_t da = desc_mnmajor(va, 8192), db = desc_mnmajor(vb, 8192);
        wgmma_fence();
#pragma unroll
        for (int kk = 0; kk < 8; kk++)
          wgmma_rs_n128_t1(o, pf[4 * kk], pf[4 * kk + 1], pf[4 * kk + 2], pf[4 * kk + 3], (kk < 4 ? da : db) + (kk & 3) * 128, 1);
        wgmma_commit();
      };
      auto epilogue = [&](int head_local, float e0, float e1) {
        e0 += __shfl_xor_sync(0xffffffffu, e0, 1); e1 += __shfl_xor_sync(0xffffffffu, e1, 1);
        e0 += __shfl_xor_sync(0xffffffffu, e0, 2); e1 += __shfl_xor_sync(0xffffffffu, e1, 2);
        const float i0 = __fdividef(1.f, e0), i1 = __fdividef(1.f, e1);
        if (p == 0) {
          const int row = mt * 128 + cw * 64 + (warp & 3) * 16 + (lane >> 2);
          bf16* op = g_o + (size_t)row * HD + (hg * 4 + head_local) * DH + (lane & 3) * 8;
#pragma unroll
          for (int mq = 0; mq < 4; mq++) {
            uint32_t a[4], b[4];
#pragma unroll
            for (int e = 0; e < 4; e++) {
              a[e] = pack_bf16(o[16 * mq + 4 * e] * i0, o[16 * mq + 4 * e + 1] * i0);
              b[e] = pack_bf16(o[16 * mq + 4 * e + 2] * i1, o[16 * mq + 4 * e + 3] * i1);
            }
            quad_transpose(a, lane); quad_transpose(b, lane);
            *(uint4*)(op + mq * 32) = make_uint4(a[0], a[1], a[2], a[3]);
            *(uint4*)(op + 8 * HD + mq * 32) = make_uint4(b[0], b[1], b[2], b[3]);
          }
        } else {
          const int mrow = cw * 64 + (warp & 3) * 16 + ((lane >> 3) & 1) * 8 + (lane & 7);
#pragma unroll
          for (int b = 0; b < 16; b += 2) {
            const int blk = b + (lane >> 4);
            const uint32_t addr = s_q + head_local * 32768 + (blk >> 3) * 16384 + mrow * 128 + (((blk & 7) ^ (lane & 7)) << 4);
            stmatrix_x4(addr, pack_bf16(o[4 * b] * i0, o[4 * b + 1] * i0), pack_bf16(o[4 * b + 2] * i1, o[4 * b + 3] * i1),
                        pack_bf16(o[4 * b + 4] * i0, o[4 * b + 5] * i0), pack_bf16(o[4 * b + 6] * i1, o[4 * b + 7] * i1));
          }
        }
      };
      issue_s(0);
      wgmma_wait<0>();
      fence_regs(s);
      release_next(); release_next();
      {
        float2 r = part_a(true);
        l0 = r.x; l1 = r.y;
        pack_a();
      }
#pragma unroll 1
      for (int t = 0; t < 7; t++) {
        if (t == 5 && p == 0) TS(wg, 32);
        issue_s((t + 1) >> 2);
        if (t == 5 && p == 0) TS(wg, 33);
        part_b();
        if (t == 5 && p == 0) TS(wg, 34);
        issue_pv();
        if (t == 5 && p == 0) TS(wg, 35);
        wgmma_wait<1>();
        fence_regs(s);
        if (t == 5 && p == 0) TS(wg, 36);
        release_next(); release_next();
        const bool first = t == 3;
        const float lp0 = l0, lp1 = l1;
        float2 r = part_a(first);
        if (t == 5 && p == 0) TS(wg, 37);
        wgmma_wait<0>();
        fence_regs(o);
        if (t == 5 && p == 0) TS(wg, 38);
        release_next(); release_next();
        if (first) epilogue(0, lp0, lp1);
        l0 = lp0 * al0 + r.x; l1 = lp1 * al1 + r.y;
        pack_a();
        TS(wg, 2 + p * 16 + t);
      }
      part_b();
      issue_pv();
      wgmma_wait<0>();
      fence_regs(o);
      release_next(); release_next();
      epilogue(1, l0, l1);
      if (p == 0) {
        asm volatile("fence.proxy.async;" ::: "memory");
        __syncwarp();
        if (lane == 0) mbar_arrive(b_oready);
      }
      TS(wg, 9 + p * 16);
    }
    {
      __syncwarp();
      uint32_t af[128];
      mbar_wait(s_bar + 8 * 4, (fph >> 4) & 1);
      {
        const int lrow = cw * 64 + (warp & 3) * 16 + ((lane >> 3) & 1) * 8 + (lane & 7);
#pragma unroll
        for (int kk = 0; kk < 32; kk++) {
          const int slab = kk >> 2, ch = (kk & 3) * 2 + (lane >> 4);
          const uint32_t base = slab < 4 ? s_ring + (4 + slab) * SLOT : s_q + (slab - 4) * 16384;
          const uint32_t addr = base + lrow * 128 + ((ch ^ (lane & 7)) << 4);
          asm volatile("ldmatrix.sync.aligned.m8n8.x4.shared.b16 {%0,%1,%2,%3}, [%4];"
                       : "=r"(af[4 * kk]), "=r"(af[4 * kk + 1]), "=r"(af[4 * kk + 2]), "=r"(af[4 * kk + 3]) : "r"(addr) : "memory");
        }
      }
      fph ^= 1u << 4;
      __syncwarp();
      if (lane == 0) {
#pragma unroll
        for (int j = 4; j < 12; j++) {
          const uint32_t slot = oproj_slot(j);
          mbar_arrive(s_bar + 8 * (A_NB + slot)); mbar_arrive_remote(r_bar + 8 * (A_NB + slot));
        }
      }
      named_bar_sync(3, 256);
      uint32_t bi = 0, ri = 0;
      auto rel = [&]() {
        const uint32_t slot = oproj_slot(ri);
        if (lane == 0) { mbar_arrive(s_bar + 8 * (A_NB + slot)); mbar_arrive_remote(r_bar + 8 * (A_NB + slot)); }
        if (++ri == 12) ri = 0;
      };
      const uint32_t s_stg = s_ring + (2 + cw) * SLOT;
      const int srow = (warp & 3) * 16 + ((lane >> 3) & 1) * 8 + (lane & 7);
      if (cw == 1) named_bar_sync(4, 256);
#pragma unroll 1
      for (int c = 0; c < 5; c++) {
        float acc[64];
#pragma unroll
        for (int i = 0; i < 64; i++) acc[i] = 0.f;
#pragma unroll
        for (int k = 0; k < 8; k++) {
          if (k == 4 && c == 0 && cw == 0) named_bar_arrive(4, 256);
          const uint32_t slot = oproj_slot(bi);
          mbar_wait(s_bar + 8 * slot, (fph >> slot) & 1);
          fph ^= 1u << slot;
          const uint64_t db = desc_mnmajor(s_ring + slot * SLOT, 8192);
          if (++bi == 12) bi = 0;
          wgmma_fence();
#pragma unroll
          for (int kk = 0; kk < 4; kk++)
            wgmma_rs_n128_t1(acc, af[16 * k + 4 * kk], af[16 * k + 4 * kk + 1], af[16 * k + 4 * kk + 2], af[16 * k + 4 * kk + 3], db + kk * 128, 1);
          wgmma_commit();
          if (k > 0) { wgmma_wait<1>(); rel(); }
        }
        wgmma_wait<0>();
        fence_regs(acc);
        rel();
        if ((tid & 127) == 0) asm volatile("cp.async.bulk.wait_group.read 0;" ::: "memory");
        named_bar_sync(1 + cw, 128);
#pragma unroll
        for (int b = 0; b < 16; b += 2) {
          const int blk = b + (lane >> 4);
          const uint32_t addr = s_stg + (blk >> 3) * 8192 + srow * 128 + (((blk & 7) ^ (lane & 7)) << 4);
          stmatrix_x4(addr, pack_bf16(acc[4 * b], acc[4 * b + 1]), pack_bf16(acc[4 * b + 2], acc[4 * b + 3]),
                      pack_bf16(acc[4 * b + 4], acc[4 * b + 5]), pack_bf16(acc[4 * b + 6], acc[4 * b + 7]));
        }
        fence_proxy_async();
        named_bar_sync(1 + cw, 128);
        if ((tid & 127) == 0) {
          tma_reduce_add_2d(&tm_part, s_stg, c * 128, mt * 128 + cw * 64);
          tma_reduce_add_2d(&tm_part, s_stg + 8192, c * 128 + 64, mt * 128 + cw * 64);
          asm volatile("cp.async.bulk.commit_group;" ::: "memory");
        }
        TS(wg, 26 + c);
      }
      if ((tid & 127) == 0) { asm volatile("cp.async.bulk.wait_group 0;" ::: "memory"); signal_done<0>(mt); }
    }
    TS(wg, 40);
    group_finish<0>(mt, hg, tid - 128, g_acc, xres, g_x1);
    TS(wg, 31);
  }
  __syncthreads();
  cluster_arrive(); cluster_wait();
  KT_END(2);
}

constexpr int F_NS = 12;
#define FFN_SKEW 1
constexpr int F_SMEM = (F_NS + 2) * SLOT + 1024 + 256;

template <int NU>
__device__ __forceinline__ void ffn_act(float (&acc)[NU * 32], uint32_t* af) {
#pragma unroll
  for (int b = 0; b < NU * 4; b++) {
    float r[4];
#pragma unroll
    for (int j = 0; j < 4; j++) {
      const float g = acc[4 * b + j], u = acc[NU * 16 + 4 * b + j];
      r[j] = g * u * rcp_approx(1.f + ex2(-1.4426950408889634f * g));
    }
    af[2 * b] = pack_bf16(r[0], r[1]);
    af[2 * b + 1] = pack_bf16(r[2], r[3]);
  }
}

__global__ void __cluster_dims__(2, 1, 1) __launch_bounds__(384, 1)
ffn_kernel(const __grid_constant__ CUtensorMap tm_a, const __grid_constant__ CUtensorMap tm_g4, const __grid_constant__ CUtensorMap tm_u4,
           const __grid_constant__ CUtensorMap tm_g1, const __grid_constant__ CUtensorMap tm_u1,
           const __grid_constant__ CUtensorMap tm_wd, const __grid_constant__ CUtensorMap tm_part,
           const bf16* __restrict__ xin, bf16* __restrict__ out) {
  extern __shared__ uint8_t smem_raw[];
  const uint32_t sbase = (smem_u32(smem_raw) + 1023) & ~1023u;
  const uint32_t s_bar = sbase + (F_NS + 2) * SLOT;
  const int tid = threadIdx.x, wg = tid >> 7, warp = tid >> 5, lane = tid & 31;
  const int mt = blockIdx.x & 15, fs = blockIdx.x >> 4;
  const int u0 = fs < 6 ? fs * 7 : 42 + (fs - 6) * 6;
  const int nu2 = fs < 6 ? 3 : 2;
  KT_BEGIN(4);
  pdl_launch();
  if (tid == 0) {
    for (int i = 0; i < F_NS; i++) { mbar_init(s_bar + 8 * i, 1); mbar_init(s_bar + 8 * (F_NS + i), 16); }
    fence_barrier_init();
  }
  __syncthreads();
  cluster_arrive(); cluster_wait();
  const uint32_t rank = cluster_ctarank();
  if (wg == 0) {
    reg_dealloc<24>();
    if (tid == 0) {
      uint32_t sl = 0, eph = 0xffffffffu;
      auto wait_empty = [&](uint32_t slot) {
        mbar_wait(s_bar + 8 * (F_NS + slot), (eph >> slot) & 1);
        eph ^= 1u << slot;
      };
      pdl_wait();
      for (int k = 0; k < 20; k++) {
        wait_empty(sl); wait_empty(sl + 1); wait_empty(sl + 2);
        const uint32_t bar = s_bar + 8 * sl, a = sbase + sl * SLOT;
        if (k < 10) {
          mbar_expect_tx(bar, 3 * SLOT);
          tma_2d(a, &tm_a, bar, k * 64, mt * 128);
          tma_3d_mc(a + SLOT + rank * SLOT, rank == 0 ? &tm_g4 : &tm_u4, bar, 0, k * 64, u0, 3);
        } else {
          mbar_expect_tx(bar, SLOT + nu2 * 8192);
          tma_2d(a, &tm_a, bar, (k - 10) * 64, mt * 128);
          for (int j = 0; j < nu2; j++)
            tma_3d_mc(a + SLOT + (rank * nu2 + j) * 4096, rank == 0 ? &tm_g1 : &tm_u1, bar, 0, (k - 10) * 64, u0 + 4 + j, 3);
        }
        sl += 3; if (sl == F_NS) sl = 0;
      }
      const int nslab = nu2 + 1;
      for (int c = 0; c < 5; c++) {
        for (int k = 0; k < nslab; k++) {
          wait_empty(sl);
          const uint32_t bar = s_bar + 8 * sl;
          mbar_expect_tx(bar, SLOT);
          tma_3d_mc(sbase + sl * SLOT + rank * 8192, &tm_wd, bar, 0, u0 * 32 + k * 64, c * 2 + rank, 3);
          if (++sl == F_NS) sl = 0;
        }
      }
    }
  } else {
    reg_alloc<240>();
    const int cw = wg - 1;
    const uint32_t r_bar = mapa(s_bar, rank ^ 1);
    uint32_t sl = 0, fph = 0, rl = 0;
    auto release = [&](int n) {
      if (lane == 0) {
        for (int i = 0; i < n; i++) { mbar_arrive(s_bar + 8 * (F_NS + rl + i)); mbar_arrive_remote(r_bar + 8 * (F_NS + rl + i)); }
      }
      rl += n; if (rl >= F_NS) rl -= F_NS;
    };
    auto mainloop = [&](auto& acc, auto mma) {
      constexpr int NR = sizeof(acc) / sizeof(float);
#pragma unroll
      for (int i = 0; i < NR; i++) acc[i] = 0.f;
#pragma unroll 1
      for (int k = 0; k < 10; k++) {
        if (NR == 128 && k == FFN_SKEW && cw == 0) named_bar_arrive(4, 256);
        mbar_wait(s_bar + 8 * sl, (fph >> sl) & 1);
        fph ^= 1u << sl;
        const uint32_t a = sbase + sl * SLOT;
        const uint64_t da = desc_kmajor(a + cw * 8192), db = desc_mn64(a + SLOT, 4096);
        sl += 3; if (sl == F_NS) sl = 0;
        wgmma_fence();
#pragma unroll
        for (int kk = 0; kk < 4; kk++) mma(acc, da + kk * 2, db + kk * 64);
        wgmma_commit();
        if (k > 0) { wgmma_wait<1>(); release(3); }
      }
      wgmma_wait<0>();
      fence_regs(acc);
      release(3);
    };
    auto down = [&](uint32_t* af, auto nk16_c) {
      constexpr int NK = decltype(nk16_c)::value;
      constexpr int NSLAB = (NK + 3) / 4;
      const uint32_t s_stg = sbase + (F_NS + cw) * SLOT;
      const int srow = (warp & 3) * 16 + ((lane >> 3) & 1) * 8 + (lane & 7);
#pragma unroll 1
      for (int c = 0; c < 5; c++) {
        float acc[64];
#pragma unroll
        for (int i = 0; i < 64; i++) acc[i] = 0.f;
#pragma unroll
        for (int k = 0; k < NSLAB; k++) {
          mbar_wait(s_bar + 8 * sl, (fph >> sl) & 1);
          fph ^= 1u << sl;
          const uint64_t db = desc_mnmajor(sbase + sl * SLOT, 8192);
          if (++sl == F_NS) sl = 0;
          wgmma_fence();
#pragma unroll
          for (int kk = 0; kk < 4; kk++)
            if (4 * k + kk < NK)
              wgmma_rs_n128_t1(acc, af[16 * k + 4 * kk], af[16 * k + 4 * kk + 1], af[16 * k + 4 * kk + 2], af[16 * k + 4 * kk + 3], db + kk * 128, 1);
          wgmma_commit();
          if (k > 0) { wgmma_wait<1>(); release(1); }
        }
        wgmma_wait<0>();
        fence_regs(acc);
        release(1);
        if ((tid & 127) == 0) asm volatile("cp.async.bulk.wait_group.read 0;" ::: "memory");
        named_bar_sync(1 + cw, 128);
#pragma unroll
        for (int b = 0; b < 16; b += 2) {
          const int blk = b + (lane >> 4);
          const uint32_t addr = s_stg + (blk >> 3) * 8192 + srow * 128 + (((blk & 7) ^ (lane & 7)) << 4);
          stmatrix_x4(addr, pack_bf16(acc[4 * b], acc[4 * b + 1]), pack_bf16(acc[4 * b + 2], acc[4 * b + 3]),
                      pack_bf16(acc[4 * b + 4], acc[4 * b + 5]), pack_bf16(acc[4 * b + 6], acc[4 * b + 7]));
        }
        fence_proxy_async();
        named_bar_sync(1 + cw, 128);
        if ((tid & 127) == 0) {
          tma_reduce_add_2d(&tm_part, s_stg, c * 128, SQ + mt * 128 + cw * 64);
          tma_reduce_add_2d(&tm_part, s_stg + 8192, c * 128 + 64, SQ + mt * 128 + cw * 64);
          asm volatile("cp.async.bulk.commit_group;" ::: "memory");
        }
      }
      if ((tid & 127) == 0) { asm volatile("cp.async.bulk.wait_group 0;" ::: "memory"); signal_done<1>(mt); }
    };
    uint32_t af[56];
    TS2(wg, 0);
    if (cw == 1) named_bar_sync(4, 256);
    {
      float acc[128];
      mainloop(acc, [](float (&d)[128], uint64_t da, uint64_t db) { wgmma_ss_n256_t1(d, da, db, 1); });
      TS2(wg, 1);
      ffn_act<4>(acc, af);
      TS2(wg, 2);
    }
    if (nu2 == 3) {
      float acc[96];
      mainloop(acc, [](float (&d)[96], uint64_t da, uint64_t db) { wgmma_ss_n192_t1(d, da, db, 1); });
      TS2(wg, 3);
      ffn_act<3>(acc, af + 32);
      TS2(wg, 4);
      down(af, IC<14>{});
      TS2(wg, 5);
    } else {
      float acc[64];
      mainloop(acc, [](float (&d)[64], uint64_t da, uint64_t db) { wgmma_ss_n128_t1(d, da, db, 1); });
      ffn_act<2>(acc, af + 32);
      down(af, IC<12>{});
    }
    group_finish<1>(mt, fs, tid - 128, g_acc + SQ * DM, g_x1, out);
  }
  __syncthreads();
  cluster_arrive(); cluster_wait();
  KT_END(4);
}

typedef CUresult (*EncodeTiledFn)(CUtensorMap*, CUtensorMapDataType, cuuint32_t, void*, const cuuint64_t*, const cuuint64_t*,
                                  const cuuint32_t*, const cuuint32_t*, CUtensorMapInterleave, CUtensorMapSwizzle,
                                  CUtensorMapL2promotion, CUtensorMapFloatOOBfill);
static EncodeTiledFn g_enc = nullptr;

static CUtensorMap map_kmajor(const void* p, uint64_t rows, uint64_t cols, uint32_t box_rows) {
  CUtensorMap m;
  cuuint64_t gd[2] = {cols, rows};
  cuuint64_t gs[1] = {cols * 2};
  cuuint32_t bx[2] = {64, box_rows};
  cuuint32_t es[2] = {1, 1};
  g_enc(&m, CU_TENSOR_MAP_DATA_TYPE_BFLOAT16, 2, (void*)p, gd, gs, bx, es, CU_TENSOR_MAP_INTERLEAVE_NONE,
        CU_TENSOR_MAP_SWIZZLE_128B, CU_TENSOR_MAP_L2_PROMOTION_L2_256B, CU_TENSOR_MAP_FLOAT_OOB_FILL_NONE);
  return m;
}
static CUtensorMap map_mnmajor(const void* p, uint64_t rows, uint64_t cols, uint32_t box_rows, uint32_t groups) {
  CUtensorMap m;
  cuuint64_t gd[3] = {64, rows, cols / 64};
  cuuint64_t gs[2] = {cols * 2, 128};
  cuuint32_t bx[3] = {64, box_rows, groups};
  cuuint32_t es[3] = {1, 1, 1};
  g_enc(&m, CU_TENSOR_MAP_DATA_TYPE_BFLOAT16, 3, (void*)p, gd, gs, bx, es, CU_TENSOR_MAP_INTERLEAVE_NONE,
        CU_TENSOR_MAP_SWIZZLE_128B, CU_TENSOR_MAP_L2_PROMOTION_L2_256B, CU_TENSOR_MAP_FLOAT_OOB_FILL_NONE);
  return m;
}

static CUtensorMap map_mn64(const void* p, uint64_t rows, uint64_t cols, uint32_t box_rows, uint32_t groups) {
  CUtensorMap m;
  cuuint64_t gd[3] = {32, rows, cols / 32};
  cuuint64_t gs[2] = {cols * 2, 64};
  cuuint32_t bx[3] = {32, box_rows, groups};
  cuuint32_t es[3] = {1, 1, 1};
  g_enc(&m, CU_TENSOR_MAP_DATA_TYPE_BFLOAT16, 3, (void*)p, gd, gs, bx, es, CU_TENSOR_MAP_INTERLEAVE_NONE,
        CU_TENSOR_MAP_SWIZZLE_64B, CU_TENSOR_MAP_L2_PROMOTION_L2_256B, CU_TENSOR_MAP_FLOAT_OOB_FILL_NONE);
  return m;
}

template <typename... KArgs, typename... Args>
static void launch_pdl(void (*kern)(KArgs...), int grid, int block, int smem, Args... args) {
  cudaLaunchConfig_t cfg = {};
  cfg.gridDim = dim3(grid); cfg.blockDim = dim3(block); cfg.dynamicSmemBytes = smem; cfg.stream = cudaStreamPerThread;
  cudaLaunchAttribute at[1];
  at[0].id = cudaLaunchAttributeProgrammaticStreamSerialization;
  at[0].val.programmaticStreamSerializationAllowed = 1;
  cfg.attrs = at; cfg.numAttrs = 1;
  cudaLaunchKernelEx(&cfg, kern, KArgs(args)...);
}

extern "C" void kernel_launch(void* const* d_in, const int* in_sizes, int n_in, void* d_out, int out_size) {
  const bf16* x = (const bf16*)d_in[0];
  const bf16* kc = (const bf16*)d_in[1];
  const bf16* vc = (const bf16*)d_in[2];
  const bf16* wq = (const bf16*)d_in[3];
  const bf16* wo = (const bf16*)d_in[4];
  const bf16* wgate = (const bf16*)d_in[6];
  const bf16* wup = (const bf16*)d_in[7];
  const bf16* wdown = (const bf16*)d_in[8];
  const bf16* c = (const bf16*)d_in[9];
  const bf16* wmod = (const bf16*)d_in[10];
  bf16* out = (bf16*)d_out;

  static bf16 *p_h = nullptr, *p_o, *p_x1, *p_h2, *p_part;
  if (!g_enc) {
    void* fn = nullptr;
    cudaDriverEntryPointQueryResult qr;
    cudaGetDriverEntryPoint("cuTensorMapEncodeTiled", &fn, cudaEnableDefault, &qr);
    g_enc = (EncodeTiledFn)fn;
    cudaGetSymbolAddress((void**)&p_h, g_h);
    cudaGetSymbolAddress((void**)&p_o, g_o);
    cudaGetSymbolAddress((void**)&p_x1, g_x1);
    cudaGetSymbolAddress((void**)&p_h2, g_h2);
    cudaGetSymbolAddress((void**)&p_part, g_acc);
    cudaFuncSetAttribute(attn_kernel, cudaFuncAttributeMaxDynamicSharedMemorySize, A_SMEM);
    cudaFuncSetAttribute(ffn_kernel, cudaFuncAttributeMaxDynamicSharedMemorySize, F_SMEM);
  }
  CUtensorMap tm_h = map_kmajor(p_h, SQ, DM, 128);
  CUtensorMap tm_wq = map_mnmajor(wq, DM, HD, 64, 1);
  CUtensorMap tm_k = map_kmajor(kc, (uint64_t)NH * SK, DH, 64);
  CUtensorMap tm_v = map_mnmajor(vc, (uint64_t)NH * SK, DH, 64, 1);
  CUtensorMap tm_o = map_kmajor(p_o, SQ, HD, 128);
  CUtensorMap tm_wo = map_mnmajor(wo, HD, DM, 64, 1);
  CUtensorMap tm_part = map_kmajor(p_part, 2 * SQ, DM, 64);
  CUtensorMap tm_h2 = map_kmajor(p_h2, SQ, DM, 128);
  CUtensorMap tm_g4 = map_mn64(wgate, DM, FF, 64, 4);
  CUtensorMap tm_u4 = map_mn64(wup, DM, FF, 64, 4);
  CUtensorMap tm_g1 = map_mn64(wgate, DM, FF, 64, 1);
  CUtensorMap tm_u1 = map_mn64(wup, DM, FF, 64, 1);
  CUtensorMap tm_wd = map_mnmajor(wdown, FF, DM, 64, 1);

  mod_kernel<<<120, 256>>>(c, wmod);
  launch_pdl(ln_kernel, SQ / 8, 256, 0, (const bf16*)x, p_h, 0, 1);
  launch_pdl(attn_kernel, 128, 384, A_SMEM, tm_h, tm_wq, tm_k, tm_v, tm_o, tm_wo, tm_part, (const bf16*)x);
  launch_pdl(ffn_kernel, 128, 384, F_SMEM, tm_h2, tm_g4, tm_u4, tm_g1, tm_u1, tm_wd, tm_part, (const bf16*)x, out);
}
```
